```python
import torch

def _softmax(x, axis=-1):
    return torch.softmax(x, dim=axis)
def _gelu(x):
    return torch.nn.functional.gelu(x, approximate="tanh")
def _silu(x):
    return torch.nn.functional.silu(x)
def _sigmoid(x):
    return torch.sigmoid(x)
def _layernorm(x, axis=-1, eps=1e-5):
    m = x.mean(dim=axis, keepdim=True)
    v = x.var(dim=axis, keepdim=True, unbiased=False)
    return (x - m) / torch.sqrt(v + eps)
def _scatter_add(tgt, idx, src, axis=0):
    return tgt.clone().index_add_(axis, idx, src)
def _segment_sum(src, seg, n):
    out = torch.zeros((n,) + src.shape[1:], dtype=src.dtype)
    return out.index_add_(0, seg, src)
def _pad(x, pw):
    flat = tuple(v for pair in reversed(pw) for v in pair)
    return torch.nn.functional.pad(x, flat)

kernel_name = 'gated_mix__softmax_full_mha__dense_activation_squared_relu__prompt'

def setup_inputs():

    _w = (lambda a: (lambda t: t.to(torch.bfloat16) if t.is_floating_point() else t)(torch.as_tensor(a)))
    def _A_setup():
        B, S, D = 1, 2048, 640
        return {
            "x": _w((lambda *s: torch.randn(*s, dtype=torch.bfloat16) * 0.05)(B, S, D)),
            "wqkv": _w((lambda *s: torch.randn(*s, dtype=torch.bfloat16) * 0.8)(D, 3 * D)),
            "wo": _w((lambda *s: torch.randn(*s, dtype=torch.bfloat16) * 0.1)(D, D)),
        }
    _A_in = _A_setup()

    def _B_setup():
        B, S, D, F = 1, 2048, 640, 1536
        return {
            "x": _w((lambda *s: torch.randn(*s, dtype=torch.bfloat16) * 0.05)(B, S, D)),
            "w1": _w((lambda *s: torch.randn(*s, dtype=torch.bfloat16) * 0.1)(D, F)),
            "b1": _w((lambda *s: torch.randn(*s, dtype=torch.bfloat16) * 0.1)(F)),
            "w2": _w((lambda *s: torch.randn(*s, dtype=torch.bfloat16) * 0.1)(F, D)),
            "b2": _w((lambda *s: torch.randn(*s, dtype=torch.bfloat16) * 0.05)(D)),
        }
    _B_in = _B_setup()

    return {
        "A_x": _A_in["x"],
        "A_wqkv": _A_in["wqkv"],
        "A_wo": _A_in["wo"],
        "B_x": _B_in["x"],
        "B_w1": _B_in["w1"],
        "B_b1": _B_in["b1"],
        "B_w2": _B_in["w2"],
        "B_b2": _B_in["b2"],
        "gate_w": _w((lambda *s: torch.randn(*s, dtype=torch.bfloat16) * 0.05)(640) * 16.0),
    }

def reference(A_x, A_wqkv, A_wo, B_x, B_w1, B_b1, B_w2, B_b2, gate_w):
    def _A_ref(x, wqkv, wo):
        B, S, D = x.shape
        H = 32; Dh = D // H
        qkv = (lambda x, *d: x.permute(*d))((x @ wqkv).reshape(B, S, 3, H, Dh), 2, 0, 3, 1, 4)
        q, k, v = qkv[0], qkv[1], qkv[2]
        scale = Dh ** -0.5
        scores = torch.einsum("bhqd,bhkd->bhqk", q, k) * scale
        p = _softmax(scores, axis=-1)
        o = torch.einsum("bhqk,bhkd->bhqd", p, v)
        return (lambda x, *d: x.permute(*d))(o, 0, 2, 1, 3).reshape(B, S, D) @ wo

    def _B_ref(x, w1, b1, w2, b2):
        h = torch.einsum("bsd,df->bsf", x, w1) + b1
        zero = torch.zeros_like(h)
        r = torch.where(h > zero, h, zero)
        h = r * r
        out = torch.einsum("bsf,fd->bsd", h, w2) + b2
        return out

    x = A_x
    g = _sigmoid((x * gate_w).sum(-1, keepdims=True))
    a = _A_ref(x, A_wqkv, A_wo)
    b = _B_ref(x, B_w1, B_b1, B_w2, B_b2)
    return g * a + (1 - g) * b
```

```cpp
#include <cuda_runtime.h>
#include <cuda_bf16.h>
#include <cuda.h>
#include <stdint.h>

__device__ __align__(1024) uint8_t g_Q[32 * 98304];
__device__ __align__(1024) uint8_t g_KV[32 * 196608];
__device__ __align__(1024) __nv_bfloat16 g_O[2048 * 640];
__device__ __align__(1024) __nv_bfloat16 g_H[2048 * 1536];
__device__ __align__(1024) uint32_t g_G[2048];
__device__ __align__(1024) uint32_t g_N[3 * 16 * 128];
__device__ __align__(1024) uint32_t g_flag[64];

__device__ __forceinline__ uint32_t s2u(const void* p) { return (uint32_t)__cvta_generic_to_shared(p); }
__device__ __forceinline__ void mbar_init(uint32_t b, uint32_t c) { asm volatile("mbarrier.init.shared::cta.b64 [%0], %1;" ::"r"(b), "r"(c)); }
__device__ __forceinline__ void mbar_init_fence() { asm volatile("fence.mbarrier_init.release.cluster;" ::: "memory"); }
__device__ __forceinline__ void mbar_expect(uint32_t b, uint32_t n) { asm volatile("mbarrier.arrive.expect_tx.shared::cta.b64 _, [%0], %1;" ::"r"(b), "r"(n) : "memory"); }
__device__ __forceinline__ void mbar_arrive(uint32_t b) { asm volatile("mbarrier.arrive.shared::cta.b64 _, [%0];" ::"r"(b) : "memory"); }
__device__ __forceinline__ void mbar_arrive_cl(uint32_t a) { asm volatile("mbarrier.arrive.shared::cluster.b64 _, [%0];" ::"r"(a) : "memory"); }
__device__ __forceinline__ void mbar_arrive_cl_n(uint32_t a, uint32_t n) { asm volatile("mbarrier.arrive.shared::cluster.b64 _, [%0], %1;" ::"r"(a), "r"(n) : "memory"); }
__device__ __forceinline__ void mbar_wait(uint32_t b, uint32_t ph) {
  asm volatile("{.reg .pred p; .reg .u32 n;\n"
               "mbarrier.try_wait.parity.shared::cta.b64 p, [%0], %1; @p bra LD; mov.u32 n, 0;\n"
               "LW: mbarrier.try_wait.parity.shared::cta.b64 p, [%0], %1; @p bra LD;\n"
               "add.u32 n, n, 1; setp.lt.u32 p, n, 2000000; @p bra LW; trap;\n"
               "LD: }" ::"r"(b), "r"(ph) : "memory");
}
__device__ __forceinline__ uint32_t mbar_test(uint32_t b, uint32_t ph) {
  uint32_t ok;
  asm volatile("{.reg .pred p; mbarrier.test_wait.parity.shared::cta.b64 p, [%1], %2; selp.u32 %0, 1, 0, p;}" : "=r"(ok) : "r"(b), "r"(ph) : "memory");
  return ok;
}
__device__ __forceinline__ void bulk_g2s(uint32_t dst, const void* g, uint32_t n, uint32_t bar) {
  asm volatile("cp.async.bulk.shared::cluster.global.mbarrier::complete_tx::bytes [%0], [%1], %2, [%3];" ::"r"(dst), "l"(g), "r"(n), "r"(bar) : "memory");
}
__device__ __forceinline__ void bulk_s2g(void* g, uint32_t src, uint32_t n) {
  asm volatile("cp.async.bulk.global.shared::cta.bulk_group [%0], [%1], %2;" ::"l"(g), "r"(src), "r"(n) : "memory");
}
__device__ __forceinline__ void tma2d(uint32_t dst, const CUtensorMap* m, int c0, int c1, uint32_t bar) {
  asm volatile("cp.async.bulk.tensor.2d.shared::cluster.global.mbarrier::complete_tx::bytes [%0], [%1, {%3, %4}], [%2];" ::"r"(dst), "l"(m), "r"(bar), "r"(c0), "r"(c1) : "memory");
}
__device__ __forceinline__ void tma2d_pair(uint32_t dst, const CUtensorMap* m, int c0, int c1, uint32_t bar) {
  asm volatile("cp.async.bulk.tensor.2d.shared::cluster.global.mbarrier::complete_tx::bytes.multicast::cluster [%0], [%1, {%3, %4}], [%2], %5;"
               ::"r"(dst), "l"(m), "r"(bar), "r"(c0), "r"(c1), "h"((uint16_t)3) : "memory");
}
__device__ __forceinline__ void tma3d_pair(uint32_t dst, const CUtensorMap* m, int c0, int c1, int c2, uint32_t bar) {
  asm volatile("cp.async.bulk.tensor.3d.shared::cluster.global.mbarrier::complete_tx::bytes.multicast::cluster [%0], [%1, {%3, %4, %5}], [%2], %6;"
               ::"r"(dst), "l"(m), "r"(bar), "r"(c0), "r"(c1), "r"(c2), "h"((uint16_t)3) : "memory");
}
__device__ __forceinline__ void tma2d_store(const CUtensorMap* m, uint32_t src, int c0, int c1) {
  asm volatile("cp.async.bulk.tensor.2d.global.shared::cta.bulk_group [%0, {%2, %3}], [%1];" ::"l"(m), "r"(src), "r"(c0), "r"(c1) : "memory");
}
__device__ __forceinline__ void tma3d_store(const CUtensorMap* m, uint32_t src, int c0, int c1, int c2) {
  asm volatile("cp.async.bulk.tensor.3d.global.shared::cta.bulk_group [%0, {%2, %3, %4}], [%1];" ::"l"(m), "r"(src), "r"(c0), "r"(c1), "r"(c2) : "memory");
}
__device__ __forceinline__ void bulk_commit() { asm volatile("cp.async.bulk.commit_group;" ::: "memory"); }
__device__ __forceinline__ void bulk_wait_all() { asm volatile("cp.async.bulk.wait_group 0;" ::: "memory"); }
__device__ __forceinline__ void bulk_wait_read() { asm volatile("cp.async.bulk.wait_group.read 0;" ::: "memory"); }
__device__ __forceinline__ void l2_prefetch(const void* g, uint32_t n) { asm volatile("cp.async.bulk.prefetch.L2.global [%0], %1;" ::"l"(g), "r"(n) : "memory"); }
__device__ __forceinline__ void tmap_prefetch(const CUtensorMap* m) { asm volatile("prefetch.tensormap [%0];" ::"l"(m) : "memory"); }
__device__ __forceinline__ void fence_async_smem() { asm volatile("fence.proxy.async.shared::cta;" ::: "memory"); }
__device__ __forceinline__ void fence_async_all() { asm volatile("fence.proxy.async;" ::: "memory"); }
__device__ __forceinline__ void fence_gpu() { asm volatile("fence.acq_rel.gpu;" ::: "memory"); }
__device__ __forceinline__ void flag_add(uint32_t* p, uint32_t target) { asm volatile("red.relaxed.gpu.global.inc.u32 [%0], %1;" ::"l"(p), "r"(target + 3) : "memory"); }
__device__ __forceinline__ void flag_wait(uint32_t* p, uint32_t target) {
  uint32_t v, n = 0;
#pragma unroll 1
  do {
    asm volatile("ld.acquire.gpu.global.u32 %0, [%1];" : "=r"(v) : "l"(p) : "memory");
    if (v >= target) break;
    __nanosleep(200);
  } while (++n < 4000000);
  if (v < target) __trap();
  flag_add(p, target);
}
__device__ __forceinline__ void cluster_sync() { asm volatile("barrier.cluster.arrive.relaxed.aligned; barrier.cluster.wait.aligned;" ::: "memory"); }
__device__ __forceinline__ uint32_t map_cta(uint32_t a, uint32_t cta) { uint32_t r; asm("mapa.shared::cluster.u32 %0, %1, %2;" : "=r"(r) : "r"(a), "r"(cta)); return r; }
__device__ __forceinline__ void pdl_wait() { asm volatile("griddepcontrol.wait;" ::: "memory"); }
__device__ __forceinline__ void pdl_launch() { asm volatile("griddepcontrol.launch_dependents;" ::: "memory"); }
__device__ __forceinline__ bool elect_one() {
  uint32_t p = 0;
  asm volatile("{.reg .pred P; elect.sync _|P, 0xffffffff; @P mov.u32 %0, 1;}" : "+r"(p));
  return p != 0;
}
__device__ __forceinline__ void sts32(uint32_t a, uint32_t v) { asm volatile("st.shared.u32 [%0], %1;" ::"r"(a), "r"(v) : "memory"); }
__device__ __forceinline__ uint32_t lds32(uint32_t a) { uint32_t v; asm volatile("ld.shared.u32 %0, [%1];" : "=r"(v) : "r"(a)); return v; }
__device__ __forceinline__ void stsm4(uint32_t a, uint32_t r0, uint32_t r1, uint32_t r2, uint32_t r3) {
  asm volatile("stmatrix.sync.aligned.m8n8.x4.shared.b16 [%0], {%1, %2, %3, %4};" ::"r"(a), "r"(r0), "r"(r1), "r"(r2), "r"(r3) : "memory");
}
__device__ __forceinline__ void wg_fence() { asm volatile("wgmma.fence.sync.aligned;" ::: "memory"); }
__device__ __forceinline__ void wg_commit() { asm volatile("wgmma.commit_group.sync.aligned;" ::: "memory"); }
template <int N> __device__ __forceinline__ void wg_wait() { asm volatile("wgmma.wait_group.sync.aligned %0;" ::"n"(N) : "memory"); }
template <int N> __device__ __forceinline__ void reg_fence(float (&d)[N]) {
#pragma unroll
  for (int i = 0; i < N; i++) asm volatile("" : "+f"(d[i])::"memory");
}
constexpr uint32_t SM0 = 1024;
__device__ __forceinline__ uint32_t smem_base(const void* p) {
  const uint32_t a = s2u(p);
  if ((a & 0xFFFFFFu) != SM0) __trap();
  return a;
}
__host__ __device__ constexpr uint64_t mkdesc(uint32_t addr, uint32_t lbo, uint32_t sbo, uint32_t swz) {
  return (uint64_t)(((addr & 0x3FFFF) >> 4) | ((lbo >> 4) << 16)) | ((uint64_t)((sbo >> 4) | (swz << 30)) << 32);
}
__device__ __forceinline__ float ex2(float x) { float y; asm("ex2.approx.ftz.f32 %0, %1;" : "=f"(y) : "f"(x)); return y; }
__device__ __forceinline__ uint32_t pack(float lo, float hi) { uint32_t r; asm("cvt.rn.bf16x2.f32 %0, %1, %2;" : "=r"(r) : "f"(hi), "f"(lo)); return r; }
__device__ __forceinline__ float bf_lo(uint32_t u) { return __uint_as_float(u << 16); }
__device__ __forceinline__ float bf_hi(uint32_t u) { return __uint_as_float(u & 0xffff0000u); }
__device__ __forceinline__ float fmax_nan(float a, float b) { float r; asm("max.NaN.f32 %0, %1, %2;" : "=f"(r) : "f"(a), "f"(b)); return r; }
__device__ __forceinline__ uint32_t bmax2_nan(uint32_t a, uint32_t b) { uint32_t r; asm("max.NaN.bf16x2 %0, %1, %2;" : "=r"(r) : "r"(a), "r"(b)); return r; }
__device__ __forceinline__ uint32_t badd2(uint32_t a, uint32_t b) { uint32_t r; asm("add.rn.bf16x2 %0, %1, %2;" : "=r"(r) : "r"(a), "r"(b)); return r; }
__device__ __forceinline__ uint32_t bmul2(uint32_t a, uint32_t b) { uint32_t r; asm("mul.rn.bf16x2 %0, %1, %2;" : "=r"(r) : "r"(a), "r"(b)); return r; }

__device__ __forceinline__ void wgmma_ss_n240(float (&d)[120], uint64_t da, uint64_t db, int acc) {
  asm volatile("{.reg .pred p; setp.ne.b32 p, %122, 0;\n"
    "wgmma.mma_async.sync.aligned.m64n240k16.f32.bf16.bf16 {%0, %1, %2, %3, %4, %5, %6, %7, %8, %9, %10, %11, %12, %13, %14, %15, %16, %17, %18, %19, %20, %21, %22, %23, %24, %25, %26, %27, %28, %29, %30, %31, %32, %33, %34, %35, %36, %37, %38, %39, %40, %41, %42, %43, %44, %45, %46, %47, %48, %49, %50, %51, %52, %53, %54, %55, %56, %57, %58, %59, %60, %61, %62, %63, %64, %65, %66, %67, %68, %69, %70, %71, %72, %73, %74, %75, %76, %77, %78, %79, %80, %81, %82, %83, %84, %85, %86, %87, %88, %89, %90, %91, %92, %93, %94, %95, %96, %97, %98, %99, %100, %101, %102, %103, %104, %105, %106, %107, %108, %109, %110, %111, %112, %113, %114, %115, %116, %117, %118, %119}, %120, %121, p, 1, 1, 0, 1;}\n"
    : "+f"(d[0]), "+f"(d[1]), "+f"(d[2]), "+f"(d[3]), "+f"(d[4]), "+f"(d[5]), "+f"(d[6]), "+f"(d[7]), "+f"(d[8]), "+f"(d[9]), "+f"(d[10]), "+f"(d[11]), "+f"(d[12]), "+f"(d[13]), "+f"(d[14]), "+f"(d[15]), "+f"(d[16]), "+f"(d[17]), "+f"(d[18]), "+f"(d[19]), "+f"(d[20]), "+f"(d[21]), "+f"(d[22]), "+f"(d[23]), "+f"(d[24]), "+f"(d[25]), "+f"(d[26]), "+f"(d[27]), "+f"(d[28]), "+f"(d[29]), "+f"(d[30]), "+f"(d[31]), "+f"(d[32]), "+f"(d[33]), "+f"(d[34]), "+f"(d[35]), "+f"(d[36]), "+f"(d[37]), "+f"(d[38]), "+f"(d[39]), "+f"(d[40]), "+f"(d[41]), "+f"(d[42]), "+f"(d[43]), "+f"(d[44]), "+f"(d[45]), "+f"(d[46]), "+f"(d[47]), "+f"(d[48]), "+f"(d[49]), "+f"(d[50]), "+f"(d[51]), "+f"(d[52]), "+f"(d[53]), "+f"(d[54]), "+f"(d[55]), "+f"(d[56]), "+f"(d[57]), "+f"(d[58]), "+f"(d[59]), "+f"(d[60]), "+f"(d[61]), "+f"(d[62]), "+f"(d[63]), "+f"(d[64]), "+f"(d[65]), "+f"(d[66]), "+f"(d[67]), "+f"(d[68]), "+f"(d[69]), "+f"(d[70]), "+f"(d[71]), "+f"(d[72]), "+f"(d[73]), "+f"(d[74]), "+f"(d[75]), "+f"(d[76]), "+f"(d[77]), "+f"(d[78]), "+f"(d[79]), "+f"(d[80]), "+f"(d[81]), "+f"(d[82]), "+f"(d[83]), "+f"(d[84]), "+f"(d[85]), "+f"(d[86]), "+f"(d[87]), "+f"(d[88]), "+f"(d[89]), "+f"(d[90]), "+f"(d[91]), "+f"(d[92]), "+f"(d[93]), "+f"(d[94]), "+f"(d[95]), "+f"(d[96]), "+f"(d[97]), "+f"(d[98]), "+f"(d[99]), "+f"(d[100]), "+f"(d[101]), "+f"(d[102]), "+f"(d[103]), "+f"(d[104]), "+f"(d[105]), "+f"(d[106]), "+f"(d[107]), "+f"(d[108]), "+f"(d[109]), "+f"(d[110]), "+f"(d[111]), "+f"(d[112]), "+f"(d[113]), "+f"(d[114]), "+f"(d[115]), "+f"(d[116]), "+f"(d[117]), "+f"(d[118]), "+f"(d[119])
    : "l"(da), "l"(db), "r"(acc));
}
__device__ __forceinline__ void wgmma_ss_n192(float (&d)[96], uint64_t da, uint64_t db, int acc) {
  asm volatile("{.reg .pred p; setp.ne.b32 p, %98, 0;\n"
    "wgmma.mma_async.sync.aligned.m64n192k16.f32.bf16.bf16 {%0, %1, %2, %3, %4, %5, %6, %7, %8, %9, %10, %11, %12, %13, %14, %15, %16, %17, %18, %19, %20, %21, %22, %23, %24, %25, %26, %27, %28, %29, %30, %31, %32, %33, %34, %35, %36, %37, %38, %39, %40, %41, %42, %43, %44, %45, %46, %47, %48, %49, %50, %51, %52, %53, %54, %55, %56, %57, %58, %59, %60, %61, %62, %63, %64, %65, %66, %67, %68, %69, %70, %71, %72, %73, %74, %75, %76, %77, %78, %79, %80, %81, %82, %83, %84, %85, %86, %87, %88, %89, %90, %91, %92, %93, %94, %95}, %96, %97, p, 1, 1, 0, 1;}\n"
    : "+f"(d[0]), "+f"(d[1]), "+f"(d[2]), "+f"(d[3]), "+f"(d[4]), "+f"(d[5]), "+f"(d[6]), "+f"(d[7]), "+f"(d[8]), "+f"(d[9]), "+f"(d[10]), "+f"(d[11]), "+f"(d[12]), "+f"(d[13]), "+f"(d[14]), "+f"(d[15]), "+f"(d[16]), "+f"(d[17]), "+f"(d[18]), "+f"(d[19]), "+f"(d[20]), "+f"(d[21]), "+f"(d[22]), "+f"(d[23]), "+f"(d[24]), "+f"(d[25]), "+f"(d[26]), "+f"(d[27]), "+f"(d[28]), "+f"(d[29]), "+f"(d[30]), "+f"(d[31]), "+f"(d[32]), "+f"(d[33]), "+f"(d[34]), "+f"(d[35]), "+f"(d[36]), "+f"(d[37]), "+f"(d[38]), "+f"(d[39]), "+f"(d[40]), "+f"(d[41]), "+f"(d[42]), "+f"(d[43]), "+f"(d[44]), "+f"(d[45]), "+f"(d[46]), "+f"(d[47]), "+f"(d[48]), "+f"(d[49]), "+f"(d[50]), "+f"(d[51]), "+f"(d[52]), "+f"(d[53]), "+f"(d[54]), "+f"(d[55]), "+f"(d[56]), "+f"(d[57]), "+f"(d[58]), "+f"(d[59]), "+f"(d[60]), "+f"(d[61]), "+f"(d[62]), "+f"(d[63]), "+f"(d[64]), "+f"(d[65]), "+f"(d[66]), "+f"(d[67]), "+f"(d[68]), "+f"(d[69]), "+f"(d[70]), "+f"(d[71]), "+f"(d[72]), "+f"(d[73]), "+f"(d[74]), "+f"(d[75]), "+f"(d[76]), "+f"(d[77]), "+f"(d[78]), "+f"(d[79]), "+f"(d[80]), "+f"(d[81]), "+f"(d[82]), "+f"(d[83]), "+f"(d[84]), "+f"(d[85]), "+f"(d[86]), "+f"(d[87]), "+f"(d[88]), "+f"(d[89]), "+f"(d[90]), "+f"(d[91]), "+f"(d[92]), "+f"(d[93]), "+f"(d[94]), "+f"(d[95])
    : "l"(da), "l"(db), "r"(acc));
}
__device__ __forceinline__ void wgmma_ss_n160(float (&d)[80], uint64_t da, uint64_t db, int acc) {
  asm volatile("{.reg .pred p; setp.ne.b32 p, %82, 0;\n"
    "wgmma.mma_async.sync.aligned.m64n160k16.f32.bf16.bf16 {%0, %1, %2, %3, %4, %5, %6, %7, %8, %9, %10, %11, %12, %13, %14, %15, %16, %17, %18, %19, %20, %21, %22, %23, %24, %25, %26, %27, %28, %29, %30, %31, %32, %33, %34, %35, %36, %37, %38, %39, %40, %41, %42, %43, %44, %45, %46, %47, %48, %49, %50, %51, %52, %53, %54, %55, %56, %57, %58, %59, %60, %61, %62, %63, %64, %65, %66, %67, %68, %69, %70, %71, %72, %73, %74, %75, %76, %77, %78, %79}, %80, %81, p, 1, 1, 0, 1;}\n"
    : "+f"(d[0]), "+f"(d[1]), "+f"(d[2]), "+f"(d[3]), "+f"(d[4]), "+f"(d[5]), "+f"(d[6]), "+f"(d[7]), "+f"(d[8]), "+f"(d[9]), "+f"(d[10]), "+f"(d[11]), "+f"(d[12]), "+f"(d[13]), "+f"(d[14]), "+f"(d[15]), "+f"(d[16]), "+f"(d[17]), "+f"(d[18]), "+f"(d[19]), "+f"(d[20]), "+f"(d[21]), "+f"(d[22]), "+f"(d[23]), "+f"(d[24]), "+f"(d[25]), "+f"(d[26]), "+f"(d[27]), "+f"(d[28]), "+f"(d[29]), "+f"(d[30]), "+f"(d[31]), "+f"(d[32]), "+f"(d[33]), "+f"(d[34]), "+f"(d[35]), "+f"(d[36]), "+f"(d[37]), "+f"(d[38]), "+f"(d[39]), "+f"(d[40]), "+f"(d[41]), "+f"(d[42]), "+f"(d[43]), "+f"(d[44]), "+f"(d[45]), "+f"(d[46]), "+f"(d[47]), "+f"(d[48]), "+f"(d[49]), "+f"(d[50]), "+f"(d[51]), "+f"(d[52]), "+f"(d[53]), "+f"(d[54]), "+f"(d[55]), "+f"(d[56]), "+f"(d[57]), "+f"(d[58]), "+f"(d[59]), "+f"(d[60]), "+f"(d[61]), "+f"(d[62]), "+f"(d[63]), "+f"(d[64]), "+f"(d[65]), "+f"(d[66]), "+f"(d[67]), "+f"(d[68]), "+f"(d[69]), "+f"(d[70]), "+f"(d[71]), "+f"(d[72]), "+f"(d[73]), "+f"(d[74]), "+f"(d[75]), "+f"(d[76]), "+f"(d[77]), "+f"(d[78]), "+f"(d[79])
    : "l"(da), "l"(db), "r"(acc));
}
__device__ __forceinline__ void wgmma_rsz_n64(float (&d)[32], uint32_t a0, uint32_t a1, uint32_t a2, uint32_t a3, uint64_t db) {
  asm volatile("{.reg .pred p; setp.ne.b32 p, 0, 0;\n"
    "wgmma.mma_async.sync.aligned.m64n64k16.f32.bf16.bf16 {%0, %1, %2, %3, %4, %5, %6, %7, %8, %9, %10, %11, %12, %13, %14, %15, %16, %17, %18, %19, %20, %21, %22, %23, %24, %25, %26, %27, %28, %29, %30, %31}, {%32,%33,%34,%35}, %36, p, 1, 1, 0;}\n"
    : "=f"(d[0]), "=f"(d[1]), "=f"(d[2]), "=f"(d[3]), "=f"(d[4]), "=f"(d[5]), "=f"(d[6]), "=f"(d[7]), "=f"(d[8]), "=f"(d[9]), "=f"(d[10]), "=f"(d[11]), "=f"(d[12]), "=f"(d[13]), "=f"(d[14]), "=f"(d[15]), "=f"(d[16]), "=f"(d[17]), "=f"(d[18]), "=f"(d[19]), "=f"(d[20]), "=f"(d[21]), "=f"(d[22]), "=f"(d[23]), "=f"(d[24]), "=f"(d[25]), "=f"(d[26]), "=f"(d[27]), "=f"(d[28]), "=f"(d[29]), "=f"(d[30]), "=f"(d[31])
    : "r"(a0), "r"(a1), "r"(a2), "r"(a3), "l"(db));
}
__device__ __forceinline__ void wgmma_rs_n64(float (&d)[32], uint32_t a0, uint32_t a1, uint32_t a2, uint32_t a3, uint64_t db) {
  asm volatile("{.reg .pred p; setp.ne.b32 p, 1, 0;\n"
    "wgmma.mma_async.sync.aligned.m64n64k16.f32.bf16.bf16 {%0, %1, %2, %3, %4, %5, %6, %7, %8, %9, %10, %11, %12, %13, %14, %15, %16, %17, %18, %19, %20, %21, %22, %23, %24, %25, %26, %27, %28, %29, %30, %31}, {%32,%33,%34,%35}, %36, p, 1, 1, 0;}\n"
    : "+f"(d[0]), "+f"(d[1]), "+f"(d[2]), "+f"(d[3]), "+f"(d[4]), "+f"(d[5]), "+f"(d[6]), "+f"(d[7]), "+f"(d[8]), "+f"(d[9]), "+f"(d[10]), "+f"(d[11]), "+f"(d[12]), "+f"(d[13]), "+f"(d[14]), "+f"(d[15]), "+f"(d[16]), "+f"(d[17]), "+f"(d[18]), "+f"(d[19]), "+f"(d[20]), "+f"(d[21]), "+f"(d[22]), "+f"(d[23]), "+f"(d[24]), "+f"(d[25]), "+f"(d[26]), "+f"(d[27]), "+f"(d[28]), "+f"(d[29]), "+f"(d[30]), "+f"(d[31])
    : "r"(a0), "r"(a1), "r"(a2), "r"(a3), "l"(db));
}
__device__ __forceinline__ void wgmma_rs_n24(float (&d)[12], uint32_t a0, uint32_t a1, uint32_t a2, uint32_t a3, uint64_t db) {
  asm volatile("{.reg .pred p; setp.ne.b32 p, 1, 0;\n"
    "wgmma.mma_async.sync.aligned.m64n24k16.f32.bf16.bf16 {%0, %1, %2, %3, %4, %5, %6, %7, %8, %9, %10, %11}, {%12,%13,%14,%15}, %16, p, 1, 1, 1;}\n"
    : "+f"(d[0]), "+f"(d[1]), "+f"(d[2]), "+f"(d[3]), "+f"(d[4]), "+f"(d[5]), "+f"(d[6]), "+f"(d[7]), "+f"(d[8]), "+f"(d[9]), "+f"(d[10]), "+f"(d[11])
    : "r"(a0), "r"(a1), "r"(a2), "r"(a3), "l"(db));
}

constexpr int K1_NS = 4, K1_SB = 16384 + 32768;
constexpr int K1_SMEM = K1_NS * K1_SB + 8192;
constexpr int K1_GAP = 800;

__global__ void __cluster_dims__(2, 1, 1) __launch_bounds__(384, 1)
k_qkv(const __grid_constant__ CUtensorMap tm_x, const __grid_constant__ CUtensorMap tm_wqkv, const __nv_bfloat16* __restrict__ x,
      const __nv_bfloat16* __restrict__ w1, const __nv_bfloat16* __restrict__ gate_w) {
  extern __shared__ __align__(1024) uint8_t smraw[];
  const uint32_t s0 = smem_base(smraw), full0 = s0 + K1_NS * K1_SB, empty0 = full0 + 8 * K1_NS, gbar = empty0 + 8 * K1_NS;
  const int tid = threadIdx.x, lane = tid & 31, warp = __shfl_sync(0xffffffffu, tid >> 5, 0);
  const int rank = blockIdx.x & 1, nb = blockIdx.x >> 4, mb = blockIdx.x & 15;
  if (warp == 8) {
    if (elect_one()) {
#pragma unroll
      for (int i = 0; i < K1_NS; i++) { mbar_init(full0 + 8 * i, 1); mbar_init(empty0 + 8 * i, 4); }
      mbar_init(gbar, 1);
      mbar_init_fence();
      mbar_expect(full0, K1_SB);
      tma2d(s0, &tm_x, 0, mb * 128, full0);
    }
    __syncwarp();
  } else if (warp == 9) {
    if (elect_one()) tmap_prefetch(&tm_wqkv);
    __syncwarp();
  }
  cluster_sync();
  pdl_launch();

  if (warp >= 8) {
    if (warp < 10) {
      if (warp == 8 && elect_one()) {
        const uint32_t t0 = clock();
#pragma unroll
        for (int s = 0; s < 10; s++) {
          const uint32_t full = full0 + 8 * (s & 3), dst = s0 + (s & 3) * K1_SB;
          if (s >= K1_NS) mbar_wait(empty0 + 8 * (s & 3), ((s >> 2) - 1) & 1);
          else while ((uint32_t)clock() - t0 < (uint32_t)(s * K1_GAP)) {}
          if (s > 0) {
            mbar_expect(full, K1_SB);
            tma2d(dst, &tm_x, s * 64, mb * 128, full);
          }
          tma2d_pair(dst + 16384 + rank * 8192, &tm_wqkv, nb * 240 + rank * 64, s * 64, full);
          tma2d_pair(dst + 16384 + (rank + 2) * 8192, &tm_wqkv, nb * 240 + (rank + 2) * 64, s * 64, full);
          if (s == 6) mbar_arrive(gbar);
        }
        l2_prefetch((const uint8_t*)w1 + blockIdx.x * 15360, 15360);
      }
      __syncwarp();
      const int wg = warp - 8, gh = nb * 12 + lane, prt = gh >> 5, head = gh & 31;
      uint8_t* dst = prt == 0 ? g_Q + (size_t)head * 98304 + (mb * 16 + wg * 8) * 384
                              : g_KV + (size_t)((head & 15) * 2 + (head >> 4)) * 196608 + mb * 12288 + (prt - 1) * 6144 + wg * 3072;
#pragma unroll
      for (int b = 0; b < 3; b++) {
        asm volatile("bar.sync %0, 160;" ::"r"(1 + wg * 3 + b) : "memory");
        if (lane >= b * (b + 1) && lane < (b + 1) * (b + 2)) { bulk_s2g(dst, s0 + (2 + wg) * K1_SB + lane * 3072, 3072); bulk_commit(); }
        __syncwarp();
      }
      if (lane < 12) bulk_wait_all();
    } else {
      mbar_wait(gbar, 0);
      uint32_t gw[10];
#pragma unroll
      for (int i = 0; i < 10; i++) gw[i] = ((const uint32_t*)gate_w)[lane + 32 * i];
      const int row0 = mb * 128 + nb * 16 + (warp - 10) * 8;
      float mine = 0.f;
#pragma unroll 4
      for (int r = 0; r < 8; r++) {
        const uint32_t* xr = (const uint32_t*)(x + (size_t)(row0 + r) * 640);
        float s = 0.f;
#pragma unroll
        for (int i = 0; i < 10; i++) { const uint32_t p = bmul2(xr[lane + 32 * i], gw[i]); s += bf_lo(p) + bf_hi(p); }
#pragma unroll
        for (int o = 16; o; o >>= 1) s += __shfl_xor_sync(0xffffffffu, s, o);
        if (lane == r) mine = s;
      }
      if (lane < 8) {
        const float g = bf_lo(pack(1.f / (1.f + __expf(-bf_lo(pack(mine, 0.f)))), 0.f));
        g_G[row0 + lane] = pack(g, 1.f - g);
      }
    }
  } else {
    const int wg = warp >> 2, t = lane & 3;
    const uint64_t dA = mkdesc(SM0, 16, 1024, 1) + wg * 512, dB = mkdesc(SM0 + 16384, 8192, 1024, 1);
    const uint32_t rel = map_cta(empty0, lane & 1);
    float acc[120];
#pragma unroll
    for (int s = 0; s < 10; s++) {
      mbar_wait(full0 + 8 * (s & 3), (s >> 2) & 1);
      wg_fence();
#pragma unroll
      for (int k = 0; k < 4; k++) wgmma_ss_n240(acc, dA + (s & 3) * (K1_SB / 16) + 2 * k, dB + (s & 3) * (K1_SB / 16) + 128 * k, s | k);
      wg_commit();
      wg_wait<1>();
      if (s > 0 && s < 9 && (tid & 127) < 2) mbar_arrive_cl(rel + ((s - 1) & 3) * 8);
    }
    wg_wait<0>();
    reg_fence(acc);
    mbar_wait(empty0 + 8 * (2 + wg), 1);
    const uint32_t stg = s0 + (2 + wg) * K1_SB;
    const int br = (lane >> 3) & 1, bc = lane >> 4, bg = (warp & 3) * 2 + br;
    const uint32_t oq0 = bg * 384 + bc * 128 + (lane & 7) * 16, ok0 = bc * 1024 + bg * 128 + (lane & 7) * 16;
    const uint32_t oq2 = bc * 3072 + bg * 384 + 256 + (lane & 7) * 16, ok2 = bc * 3072 + 2048 + bg * 128 + (lane & 7) * 16;
#pragma unroll
    for (int hp = 0; hp < 6; hp++) {
      const int part = (nb * 6 + hp) >> 4;
      float* v = &acc[20 * hp];
      if (part == 0) {
#pragma unroll
        for (int i = 0; i < 20; i++) v[i] *= 0.32259642f;
      }
      const uint32_t pad = (lane & 1) ? 0u : part == 1 ? 0x3F804740u : 0x3F80u;
      const uint32_t m0 = pack(v[8], v[9]), m1 = pack(v[10], v[11]), ha = stg + hp * 6144;
      stsm4(ha + (part == 1 ? ok0 : oq0), pack(v[0], v[1]), pack(v[2], v[3]), pack(v[4], v[5]), pack(v[6], v[7]));
      stsm4(ha + 3072 + (part == 1 ? ok0 : oq0), pack(v[12], v[13]), pack(v[14], v[15]), pack(v[16], v[17]), pack(v[18], v[19]));
      stsm4(ha + (part == 1 ? ok2 : oq2), t < 2 ? m0 : pad, t < 2 ? m1 : pad, t < 2 ? pad : m0, t < 2 ? pad : m1);
      if (hp == 0 || hp == 2 || hp == 5) {
        fence_async_smem();
        asm volatile("bar.arrive %0, 160;" ::"r"(1 + wg * 3 + (hp >> 1)) : "memory");
      }
    }
    uint32_t n2[6], n3[6];
#pragma unroll
    for (int hp = 0; hp < 6; hp++) {
      const float* v = &acc[20 * hp];
      const float mid0 = v[8] * v[8] + v[9] * v[9], mid1 = v[10] * v[10] + v[11] * v[11];
      n2[hp] = pack(v[0] * v[0] + v[1] * v[1] + v[4] * v[4] + v[5] * v[5] + (t < 2 ? mid0 : 0.f),
                    v[12] * v[12] + v[13] * v[13] + v[16] * v[16] + v[17] * v[17] + (t < 2 ? 0.f : mid0));
      n3[hp] = pack(v[2] * v[2] + v[3] * v[3] + v[6] * v[6] + v[7] * v[7] + (t < 2 ? mid1 : 0.f),
                    v[14] * v[14] + v[15] * v[15] + v[18] * v[18] + v[19] * v[19] + (t < 2 ? 0.f : mid1));
    }
#pragma unroll
    for (int o = 1; o < 4; o <<= 1) {
#pragma unroll
      for (int hp = 0; hp < 6; hp++) {
        n2[hp] = badd2(n2[hp], __shfl_xor_sync(0xffffffffu, n2[hp], o));
        n3[hp] = badd2(n3[hp], __shfl_xor_sync(0xffffffffu, n3[hp], o));
      }
    }
#pragma unroll
    for (int hp = 0; hp < 6; hp++) n2[hp] = bmax2_nan(n2[hp], n3[hp]);
#pragma unroll
    for (int o = 4; o < 32; o <<= 1) {
#pragma unroll
      for (int hp = 0; hp < 6; hp++) n2[hp] = bmax2_nan(n2[hp], __shfl_xor_sync(0xffffffffu, n2[hp], o));
    }
    uint32_t mine = n2[0];
#pragma unroll
    for (int hp = 1; hp < 6; hp++) mine = lane == hp ? n2[hp] : mine;
    if (lane < 6) g_N[(nb * 6 + lane) * 128 + mb * 8 + warp] = mine;
  }
}

constexpr int K2_NS = 3, K2_SB = 24576;
constexpr int K2_SS = K2_SB + 256;
constexpr int K2_SMEM = K2_NS * K2_SS + 12288 + 1024 + 2176 + 384;

struct ExpC { uint32_t a; };
__device__ __forceinline__ uint32_t exp2_pair(float t0, float t1, const ExpC& c) {
  uint32_t y, n, z, w, p;
  asm("prmt.b32 %0, %1, %2, 0x7430;" : "=r"(y) : "r"(__float_as_uint(t0)), "r"(__float_as_uint(t1)));
  asm("prmt.b32 %0, %1, %2, 0xF5B1;" : "=r"(n) : "r"(__float_as_uint(t0)), "r"(__float_as_uint(t1)));
  asm("fma.rn.f16x2 %0, %1, %2, %3;" : "=r"(z) : "r"(y), "r"(c.a), "r"(0x3d273d27u));
  asm("fma.rn.f16x2 %0, %1, %1, %2;" : "=r"(w) : "r"(z), "r"(0x346d346du));
  asm("fma.rn.f16x2 %0, %1, %2, %3;" : "=r"(p) : "r"(w), "r"(z), "r"(0xbf3bbf3cu));
  return n * 128 + p;
}
template <int H> __device__ __forceinline__ void exp_pv(const float (&s)[32], uint32_t (&p)[16], float (&o)[12], uint64_t dv, const ExpC& c) {
#pragma unroll
  for (int i = 4 * H; i < 4 * H + 4; i++) {
    p[2 * i + 1] = pack(ex2(s[4 * i + 2]), ex2(s[4 * i + 3]));
    p[2 * i] = exp2_pair(s[4 * i], s[4 * i + 1], c);
  }
  wg_fence();
#pragma unroll
  for (int k = 2 * H; k < 2 * H + 2; k++) wgmma_rs_n24(o, p[4 * k], p[4 * k + 1], p[4 * k + 2], p[4 * k + 3], dv + k * 48);
}
__device__ __forceinline__ void qk(float (&s)[32], const uint32_t (&q)[8], uint64_t dk) {
  wgmma_rsz_n64(s, q[0], q[1], q[2], q[3], dk);
  wgmma_rs_n64(s, q[4], q[5], q[6], q[7], dk + 64);
}
__device__ __forceinline__ uint32_t ring_release(uint32_t cnt, uint32_t lim) {
  uint32_t old;
  asm volatile("atom.shared.inc.u32 %0, [%1], %2;" : "=r"(old) : "r"(cnt), "r"(lim) : "memory");
  return old;
}
__device__ __forceinline__ void ring_refill(uint32_t old, int gs, uint32_t slot, const uint8_t* KVh) {
  if (__any_sync(0xffffffffu, old == ((gs >= 1 && gs <= 16 - K2_NS) ? 15u : 16u))) {
    if (elect_one()) {
      mbar_expect(slot + K2_SB + 128, K2_SB);
      bulk_g2s(slot, KVh + (gs - 1 + K2_NS) * K2_SB, K2_SB, slot + K2_SB + 128);
    }
    __syncwarp();
  }
}
__device__ __forceinline__ void load_q_smem(uint32_t (&q)[8], uint32_t a) {
#pragma unroll
  for (int i = 0; i < 4; i++) q[i] = lds32(a + (i >> 1) * 128 + (i & 1) * 384);
  q[6] = lds32(a + 256);
  q[7] = lds32(a + 256 + 384);
}
__device__ __forceinline__ void load_q_global(uint32_t (&q)[8], const uint32_t* g, uint32_t za) {
#pragma unroll
  for (int i = 0; i < 4; i++) q[i] = __ldcg(g + (i >> 1) * 32 + (i & 1) * 96);
  q[6] = __ldcg(g + 64);
  q[7] = __ldcg(g + 64 + 96);
  q[4] = lds32(za);
  q[5] = lds32(za + 128);
}
__device__ __forceinline__ uint32_t lds_max4(uint32_t a) {
  uint32_t v[4];
  asm volatile("ld.shared.v4.u32 {%0, %1, %2, %3}, [%4];" : "=r"(v[0]), "=r"(v[1]), "=r"(v[2]), "=r"(v[3]) : "r"(a));
  return bmax2_nan(bmax2_nan(v[0], v[1]), bmax2_nan(v[2], v[3]));
}
__device__ __forceinline__ bool shift_is_safe(uint32_t sN, int lane, int odd) {
  const uint32_t q2 = lds32(sN + 2048 + lane * 4), sel = odd ? 0x7632 : 0x5410;
  const uint32_t k2 = bmax2_nan(lds_max4(sN + lane * 16), lds_max4(sN + 512 + lane * 16));
  uint32_t qk = __byte_perm(q2, k2, sel), vv = __byte_perm(lds_max4(sN + 1024 + lane * 16), lds_max4(sN + 1536 + lane * 16), sel);
#pragma unroll
  for (int o = 16; o; o >>= 1) {
    qk = bmax2_nan(qk, __shfl_xor_sync(0xffffffffu, qk, o));
    vv = bmax2_nan(vv, __shfl_xor_sync(0xffffffffu, vv, o));
  }
  const float v0 = bf_lo(vv), v1 = bf_hi(vv);
  return bf_lo(qk) * bf_hi(qk) <= 2350.f && v0 >= 5.9604645e-8f && v1 >= 5.9604645e-8f && v0 <= 1e30f && v1 <= 1e30f;
}
struct Epi { uint32_t off, ga, src; int tail; };
__device__ __forceinline__ void store_o(const float (&o)[12], const Epi& e, int u) {
  const uint32_t g0 = lds32(e.ga), g1 = lds32(e.ga + 32);
  const float l0 = __shfl_sync(0xffffffffu, o[8], e.src), l1 = __shfl_sync(0xffffffffu, o[10], e.src);
  const float r0 = __fdividef(bf_lo(g0), l0), r1 = __fdividef(bf_lo(g1), l1);
  uint32_t* p0 = (uint32_t*)g_O + e.off + u * 160;
  uint32_t* p1 = p0 + 8 * 320;
  p0[0] = pack(o[0] * r0, o[1] * r0); p1[0] = pack(o[2] * r1, o[3] * r1);
  p0[4] = pack(o[4] * r0, o[5] * r0); p1[4] = pack(o[6] * r1, o[7] * r1);
  if (e.tail) { p0[e.tail] = pack(o[8] * r0, o[9] * r0); p1[e.tail] = pack(o[10] * r1, o[11] * r1); }
}
__device__ __forceinline__ void signal_o(uint32_t obar, uint32_t tok, int qb, int lane) {
  uint32_t old = 1;
  if (lane == 0) asm volatile("atom.shared.exch.b32 %0, [%1], 1;" : "=r"(old) : "r"(tok) : "memory");
  if (old == 0) {
    mbar_wait(obar, 0);
    fence_gpu();
#pragma unroll
    for (int i = 0; i < 4; i++) flag_add(g_flag + 32 + qb * 4 + i, 16);
  }
  __syncwarp();
}
__device__ __forceinline__ void ldsm4(uint32_t* b, uint32_t a) { asm volatile("ldmatrix.sync.aligned.m8n8.x4.shared.b16 {%0,%1,%2,%3}, [%4];" : "=r"(b[0]), "=r"(b[1]), "=r"(b[2]), "=r"(b[3]) : "r"(a)); }
__device__ __forceinline__ void ldsm2(uint32_t* b, uint32_t a) { asm volatile("ldmatrix.sync.aligned.m8n8.x2.shared.b16 {%0,%1}, [%2];" : "=r"(b[0]), "=r"(b[1]) : "r"(a)); }
__device__ __forceinline__ void ldsm4t(uint32_t* b, uint32_t a) { asm volatile("ldmatrix.sync.aligned.m8n8.x4.trans.shared.b16 {%0,%1,%2,%3}, [%4];" : "=r"(b[0]), "=r"(b[1]), "=r"(b[2]), "=r"(b[3]) : "r"(a)); }
__device__ __forceinline__ void ldsm2t(uint32_t* b, uint32_t a) { asm volatile("ldmatrix.sync.aligned.m8n8.x2.trans.shared.b16 {%0,%1}, [%2];" : "=r"(b[0]), "=r"(b[1]) : "r"(a)); }
__device__ __forceinline__ void hmma16(float* d, uint32_t a0, uint32_t a1, uint32_t a2, uint32_t a3, uint32_t b0, uint32_t b1) {
  asm("mma.sync.aligned.m16n8k16.row.col.f32.bf16.bf16.f32 {%0,%1,%2,%3}, {%4,%5,%6,%7}, {%8,%9}, {%0,%1,%2,%3};"
      : "+f"(d[0]), "+f"(d[1]), "+f"(d[2]), "+f"(d[3]) : "r"(a0), "r"(a1), "r"(a2), "r"(a3), "r"(b0), "r"(b1));
}
__device__ __forceinline__ void hmma8(float* d, uint32_t a0, uint32_t a1, uint32_t b0) {
  asm("mma.sync.aligned.m16n8k8.row.col.f32.bf16.bf16.f32 {%0,%1,%2,%3}, {%4,%5}, {%6}, {%0,%1,%2,%3};"
      : "+f"(d[0]), "+f"(d[1]), "+f"(d[2]), "+f"(d[3]) : "r"(a0), "r"(a1), "r"(b0));
}

__global__ void __maxnreg__(96) k_attn() {
  extern __shared__ __align__(1024) uint8_t smraw[];
  const int h = blockIdx.x >> 3, qb = blockIdx.x & 7, odd = h & 1;
  const int tid = threadIdx.x, lane = tid & 31, warp = __shfl_sync(0xffffffffu, tid >> 5, 0), wg = warp >> 2, t = lane & 3;
  const uint32_t sKV = smem_base(smraw), sQ = sKV + K2_NS * K2_SS, sG = sQ + 12288, sN = sG + 1024, sZ = sN + 2176;
  const uint32_t full0 = sKV + K2_SB + 128, qbar = sZ + 256, fbar = qbar + 8, obar = qbar + 16, otok = qbar + 24, sC = qbar + 32, cbar = qbar + 64;
  const uint8_t* KVh = g_KV + (size_t)h * 393216;
  if (tid == 0) {
#pragma unroll
    for (int i = 0; i < K2_NS; i++) mbar_init(full0 + K2_SS * i, 1);
    mbar_init(qbar, 1); mbar_init(fbar, 1); mbar_init(obar, 16); mbar_init(cbar, 1);
    sts32(otok, 0); sts32(sC, 0xb2d7b2d7u);
    mbar_init_fence();
  }
  if (tid < 64) sts32(sZ + tid * 4, 0);
  if (warp >= 2 && warp < 2 + K2_NS) sts32(sKV + (warp - 2) * K2_SS + K2_SB + lane * 4, 0);
  __syncthreads();
  pdl_launch();
  pdl_wait();
  if (warp == 0 && elect_one()) {
    mbar_expect(fbar, K2_SB / 2 + 2176);
    bulk_g2s(sKV, KVh, K2_SB / 2, fbar);
#pragma unroll
    for (int i = 0; i < 4; i++) bulk_g2s(sN + i * 512, g_N + (16 + 8 * i + (h >> 1)) * 128, 512, fbar);
#pragma unroll
    for (int i = 0; i < 2; i++) bulk_g2s(sN + 2048 + i * 64, g_N + (8 * i + (h >> 1)) * 128 + qb * 16, 64, fbar);
    mbar_expect(full0, K2_SB / 2);
    bulk_g2s(sKV + K2_SB / 2, KVh + K2_SB / 2, K2_SB / 2, full0);
  }
  const int lrow = wg * 64 + (warp & 3) * 16, row = qb * 256 + lrow + (lane >> 2);
  const uint32_t* qg = (const uint32_t*)(g_Q + (size_t)h * 98304 + qb * 12288 + (lrow >> 3) * 384) + lane;
  auto keep = [&](uint32_t v) { return __shfl_sync(0xffffffffu, v, lane); };
  const uint32_t cnta = keep(sKV + K2_SB + lane * 4), lim = keep(lane == 0 ? 15 : 0);
  const uint32_t qa = keep(sQ + (lrow >> 3) * 384 + lane * 4);
  Epi e;
  e.off = keep(row * 320 + h * 10 + t + odd * 2);
  e.ga = sG + (row & 255) * 4;
  e.src = (lane & ~3) | (odd ? 0 : 2);
  e.tail = keep(((t >> 1) ^ odd) ? 0 : odd ? -4 : 8);
  const uint32_t pad0 = keep((t & 1) ? 0u : 0xC2503F80u), pad1 = (t & 1) ? 0u : 0xC2500000u;
  uint32_t safe = 1;
  {
    uint32_t q[8], p[16];
    float s[32], o[12];
    load_q_global(q, qg, sZ + lane * 4);
    if (!e.tail) { q[6] = pad0; q[7] = pad1; }
    ExpC c;
    c.a = lds32(sC);
    constexpr uint64_t dK = mkdesc(SM0, 1024, 128, 0);
    constexpr int VO = (int)(mkdesc(SM0 + 6144, 384, 128, 0) - dK);
    uint32_t so = 0, sp = (K2_NS - 1) * K2_SS, ph = 0, ready = 1;
    mbar_wait(fbar, 0);
    if (warp == 15) {
      if (elect_one()) {
#pragma unroll
        for (int i = 1; i < K2_NS; i++) { mbar_expect(full0 + i * K2_SS, K2_SB); bulk_g2s(sKV + i * K2_SS, KVh + i * K2_SB, K2_SB, full0 + i * K2_SS); }
        mbar_expect(qbar, 12288 + 1024);
        bulk_g2s(sQ, g_Q + (size_t)(h + 16) * 98304 + qb * 12288, 12288, qbar);
        bulk_g2s(sG, g_G + qb * 256, 1024, qbar);
      }
      __syncwarp();
    } else if (warp == 0) {
      const bool ok = shift_is_safe(sN, lane, odd);
      if (lane == 0) { sts32(cbar + 8, ok); mbar_arrive(cbar); }
      __syncwarp();
    }
    int gs = 0;
#pragma unroll 1
    for (int u = 0; safe && u < 2; u++) {
      if (u) {
        mbar_wait(qbar, 0);
        load_q_smem(q, qa);
        if (!e.tail) { q[6] = pad0; q[7] = pad1; }
        store_o(o, e, 0);
        __syncwarp();
        if (lane == 0) mbar_arrive(obar);
      }
#pragma unroll
      for (int i = 0; i < 12; i++) o[i] = 0.f;
      reg_fence(o);
#pragma unroll 1
      do {
        if (!ready) mbar_wait(full0 + so, ph);
        const uint64_t kd = (dK & 0xffffffff00000000ull) | ((uint32_t)dK + (so >> 4));
        wg_fence();
        qk(s, q, kd);
        wg_commit();
        const bool wrap = so == (K2_NS - 1) * K2_SS;
        const int step = wrap ? -(K2_NS - 1) * K2_SS : K2_SS;
        uint32_t old = 0;
#pragma unroll
        for (int jj = 0; jj < 4; jj++) {
          const int off = (jj >> 1) * 768 + (jj & 1) * 192, offn = ((jj + 1) >> 1) * 768 + ((jj + 1) & 1) * 192;
          wg_wait<0>();
          reg_fence(s);
          if (jj == 2) { if (wrap) ph ^= 1; ready = mbar_test(full0 + so + step, ph); }
          exp_pv<0>(s, p, o, kd + (VO + off), c);
          exp_pv<1>(s, p, o, kd + (VO + off), c);
          if (jj == 1 && gs == 0) { wg_commit(); mbar_wait(full0, 0); mbar_wait(cbar, 0); safe = __any_sync(0xffffffffu, lds32(cbar + 8)); wg_fence(); }
          if (jj < 3) qk(s, q, kd + offn);
          wg_commit();
          if (jj == 0) old = ring_release(cnta + sp, lim);
          if (jj == 1) ring_refill(old, gs, sKV + sp, KVh);
          if (jj == 2 && gs == 10) signal_o(obar, otok, qb, lane);
        }
        sp = so; so += step;
      } while ((++gs & 7) && safe);
      wg_wait<0>();
      reg_fence(o);
    }
    if (safe) store_o(o, e, 1);
  }
  if (!safe) {
    const int mi = lane >> 3, r16 = (lane & 7) * 16;
    const uint32_t ka = (mi >> 1) * 128 + (mi & 1) * 1024 + r16, kt = 2048 + (mi & 1) * 128 + r16;
    const uint32_t va = (mi & 1) * 384 + (mi >> 1) * 128 + r16, vt = 256 + (mi & 1) * 384 + r16;
    uint32_t so = 0, sp = (K2_NS - 1) * K2_SS, ph = 0;
    mbar_wait(qbar, 0);
#pragma unroll 1
    for (int u = 0; u < 2; u++) {
      uint32_t q[8];
      float o[12], m0 = -INFINITY, m1 = -INFINITY;
      if (u) load_q_smem(q, qa); else load_q_global(q, qg, sZ + lane * 4);
      if (!e.tail) q[6] = q[7] = 0;
#pragma unroll
      for (int i = 0; i < 12; i++) o[i] = 0.f;
#pragma unroll 1
      for (int st = 0; st < 8; st++) {
        ring_refill(ring_release(cnta + sp, lim), u * 8 + st, sKV + sp, KVh);
        mbar_wait(full0 + so, ph);
#pragma unroll 1
        for (int sub = 0; sub < 8; sub++) {
          const uint32_t kb = sKV + so + (sub >> 2) * 12288 + (sub & 2) * 1536 + (sub & 1) * 512;
          const uint32_t vb = sKV + so + (sub >> 2) * 12288 + 6144 + (sub & 3) * 1536;
          float s[16];
#pragma unroll
          for (int i = 0; i < 16; i++) s[i] = 0.f;
#pragma unroll
          for (int b2 = 0; b2 < 2; b2++) {
            uint32_t f[6];
            ldsm4(f, kb + b2 * 256 + ka); ldsm2(f + 4, kb + b2 * 256 + kt);
            hmma16(s + 8 * b2, q[0], q[1], q[2], q[3], f[0], f[1]); hmma8(s + 8 * b2, q[6], q[7], f[4]);
            hmma16(s + 8 * b2 + 4, q[0], q[1], q[2], q[3], f[2], f[3]); hmma8(s + 8 * b2 + 4, q[6], q[7], f[5]);
          }
          float x0 = m0, x1 = m1;
#pragma unroll
          for (int i = 0; i < 4; i++) { x0 = fmax_nan(x0, fmax_nan(s[4 * i], s[4 * i + 1])); x1 = fmax_nan(x1, fmax_nan(s[4 * i + 2], s[4 * i + 3])); }
          x0 = fmax_nan(x0, __shfl_xor_sync(0xffffffffu, x0, 1)); x1 = fmax_nan(x1, __shfl_xor_sync(0xffffffffu, x1, 1));
          x0 = fmax_nan(x0, __shfl_xor_sync(0xffffffffu, x0, 2)); x1 = fmax_nan(x1, __shfl_xor_sync(0xffffffffu, x1, 2));
          const float u0 = x0 == -INFINITY ? 0.f : x0, u1 = x1 == -INFINITY ? 0.f : x1;
          const float f0 = ex2(m0 - u0), f1 = ex2(m1 - u1);
          m0 = x0; m1 = x1;
#pragma unroll
          for (int i = 0; i < 3; i++) { o[4 * i] *= f0; o[4 * i + 1] *= f0; o[4 * i + 2] *= f1; o[4 * i + 3] *= f1; }
#pragma unroll
          for (int b2 = 0; b2 < 2; b2++) {
            const float* z = s + 8 * b2;
            const uint32_t a0 = pack(ex2(z[0] - u0), ex2(z[1] - u0)), a1 = pack(ex2(z[2] - u1), ex2(z[3] - u1));
            const uint32_t a2 = pack(ex2(z[4] - u0), ex2(z[5] - u0)), a3 = pack(ex2(z[6] - u1), ex2(z[7] - u1));
            uint32_t f[6];
            ldsm4t(f, vb + b2 * 768 + va); ldsm2t(f + 4, vb + b2 * 768 + vt);
            hmma16(o, a0, a1, a2, a3, f[0], f[1]); hmma16(o + 4, a0, a1, a2, a3, f[2], f[3]); hmma16(o + 8, a0, a1, a2, a3, f[4], f[5]);
          }
        }
        __syncwarp();
        sp = so; so += K2_SS;
        if (so == K2_NS * K2_SS) { so = 0; ph ^= 1; }
      }
      store_o(o, e, u);
      if (u == 0) {
        __syncwarp();
        if (lane == 0) mbar_arrive(obar);
        signal_o(obar, otok, qb, lane);
      }
    }
  }
}

constexpr int K3_NS = 4, K3_SB = 32768;
constexpr int K3_SMEM = K3_NS * K3_SB + 64;
struct K3Maps { CUtensorMap x, h, o, w1, w2, wo, out; };
struct K3Ctx { uint32_t s0, full0, empty0, rel; int rank, j, rb, warp, lane; };

template <int N, bool PACED> __device__ __forceinline__ void k3_mma(float (&acc)[N / 2], const K3Ctx& c, int slot, uint32_t ph, int first) {
  const uint64_t a = mkdesc(SM0, 16, 1024, 1) + slot * (K3_SB / 16);
  const uint64_t b = (N == 192 ? mkdesc(SM0 + 8192, 4096, 1024, 1) : mkdesc(SM0 + 8192, 2048, 512, 2)) + slot * (K3_SB / 16);
  mbar_wait(c.full0 + slot * 8, ph);
  wg_fence();
#pragma unroll
  for (int k = 0; k < 4; k++) {
    if constexpr (N == 192) wgmma_ss_n192(acc, a + 2 * k, b + (k >> 1) * 768 + (k & 1) * 128, k | !first);
    else wgmma_ss_n160(acc, a + 2 * k, b + (k >> 1) * 640 + (k & 1) * 64, k | !first);
    if (PACED && k == 1) { wg_commit(); wg_wait<0>(); wg_fence(); }
  }
  wg_commit();
}
__device__ __forceinline__ void k3_release(const K3Ctx& c, int slot) { if (c.lane < 2) mbar_arrive_cl(c.rel + slot * 8); }
__device__ __forceinline__ void k3_fill(const K3Ctx& c, int slot, int wait_ph, const CUtensorMap* ma, const CUtensorMap* mb, int k0, int blk, int half) {
  if (c.warp < 2) {
    if (wait_ph >= 0) mbar_wait(c.empty0 + slot * 8, wait_ph);
    if (elect_one()) {
      const uint32_t dst = c.s0 + slot * K3_SB, bar = c.full0 + slot * 8;
      if (c.warp == 0) {
        mbar_expect(bar, 8192 + 2 * half);
        tma3d_pair(dst + 8192 + c.rank * half, mb, 0, k0 + c.rank * 32, blk, bar);
      } else if (ma) {
        tma2d(dst, ma, k0, c.rb * 64, bar);
      }
    }
    __syncwarp();
  }
}
template <int S> __device__ __forceinline__ void k3_fill_stage(const K3Ctx& c, const K3Maps& m) {
  constexpr int W = S >= K3_NS ? ((S / K3_NS) - 1) & 1 : -1;
  if constexpr (S < 20) k3_fill(c, S & 3, W, &m.x, &m.w1, (S % 10) * 64, c.j * 6 + (S / 10) * 3, 12288);
  else if constexpr (S < 22) {
    if (S == 20 && c.warp == 1) { if (elect_one()) bulk_wait_all(); __syncwarp(); }
    k3_fill(c, S & 3, W, &m.h, &m.w2, (c.j * 6 + S - 20) * 64, c.j * 5, 10240);
  }
  else k3_fill(c, S & 3, W, (S >= 49 && S < 53) ? nullptr : &m.o, &m.wo, (S - 44) * 64, c.j * 5, 10240);
}
template <int S, int E> __device__ __forceinline__ void k3_ffn1_stages(float (&acc)[96], const K3Ctx& c, const K3Maps& m) {
  if constexpr (S < E) {
    k3_mma<192, true>(acc, c, S & 3, (S / K3_NS) & 1, S % 10 == 0);
    if constexpr (S >= 2) k3_fill_stage<S + 2>(c, m);
    wg_wait<1>();
    if constexpr (S % 10 != 0) k3_release(c, (S - 1) & 3);
    k3_ffn1_stages<S + 1, E>(acc, c, m);
  }
}
template <int T> __device__ __forceinline__ void k3_ffn1_tile(const K3Ctx& c, const K3Maps& m, const __nv_bfloat16* __restrict__ b1) {
  float acc[96];
  k3_ffn1_stages<10 * T, 10 * T + 10>(acc, c, m);
  wg_wait<0>();
  reg_fence(acc);
  __syncthreads();
  constexpr int SL = (10 * T + 9) & 3;
  const uint32_t stg = c.s0 + SL * K3_SB;
  const int mi = c.lane >> 3, srow = c.warp * 16 + (mi & 1) * 8 + (c.lane & 7);
#pragma unroll
  for (int i = 0; i < 12; i++) {
    uint32_t w[4];
#pragma unroll
    for (int q = 0; q < 4; q++) {
      const uint32_t bb = __ldg((const uint32_t*)b1 + c.j * 192 + T * 96 + (2 * i + (q >> 1)) * 4 + (c.lane & 3));
      uint32_t r;
      asm("fma.rn.relu.bf16x2 %0, %1, %2, %3;" : "=r"(r) : "r"(pack(acc[8 * i + 2 * q], acc[8 * i + 2 * q + 1])), "r"(0x3F803F80u), "r"(bb));
      w[q] = bmul2(r, r);
    }
    const int chunk = ((2 * i) & 7) + (mi >> 1);
    stsm4(stg + (i >> 2) * 8192 + srow * 128 + ((chunk ^ (srow & 7)) << 4), w[0], w[1], w[2], w[3]);
  }
  fence_async_smem();
  __syncthreads();
  if (c.warp == 1) {
    if (elect_one()) {
#pragma unroll
      for (int i = 0; i < 3; i++) tma2d_store(&m.h, stg + i * 8192, c.j * 384 + T * 192 + i * 64, c.rb * 64);
      bulk_commit();
      bulk_wait_read();
      mbar_arrive_cl_n(map_cta(c.empty0 + SL * 8, 0), 4);
      mbar_arrive_cl_n(map_cta(c.empty0 + SL * 8, 1), 4);
    }
    __syncwarp();
  }
}
template <int S, int E> __device__ __forceinline__ void k3_wo_stages(float (&acc)[80], const K3Ctx& c, const K3Maps& m) {
  if constexpr (S < E) {
    k3_mma<160, false>(acc, c, S & 3, (S / K3_NS) & 1, 0);
    if constexpr (S < 49) k3_fill_stage<S + 2>(c, m);
    wg_wait<1>();
    if constexpr (S != 44 && S != 49 && S <= 50) k3_release(c, (S - 1) & 3);
    if constexpr (S == 50) k3_fill_stage<53>(c, m);
    k3_wo_stages<S + 1, E>(acc, c, m);
  }
}

__global__ void __cluster_dims__(2, 1, 1) __maxnreg__(128)
k_ffn(const __grid_constant__ K3Maps m, const __nv_bfloat16* __restrict__ b1, const __nv_bfloat16* __restrict__ b2,
      const __nv_bfloat16* __restrict__ w2, const __nv_bfloat16* __restrict__ wo) {
  extern __shared__ __align__(1024) uint8_t smraw[];
  K3Ctx c;
  const int tid = threadIdx.x, cl = blockIdx.x >> 1;
  c.s0 = smem_base(smraw); c.full0 = c.s0 + K3_NS * K3_SB; c.empty0 = c.full0 + 8 * K3_NS;
  c.lane = tid & 31; c.warp = __shfl_sync(0xffffffffu, tid >> 5, 0);
  c.rank = blockIdx.x & 1; c.j = (cl >> 3) & 3; c.rb = (((cl & 7) | ((cl >> 5) << 3)) << 1) | c.rank;
  c.rel = map_cta(c.empty0, c.lane & 1);
  if (tid == 0) {
#pragma unroll
    for (int i = 0; i < K3_NS; i++) { mbar_init(c.full0 + i * 8, 1); mbar_init(c.empty0 + i * 8, 8); }
    mbar_init_fence();
  }
  __syncwarp();
  cluster_sync();
  k3_fill_stage<0>(c, m); k3_fill_stage<1>(c, m); k3_fill_stage<2>(c, m); k3_fill_stage<3>(c, m);
  if (c.warp == 3) {
    if (elect_one()) {
      l2_prefetch((const uint8_t*)w2 + blockIdx.x * 15360, 15360);
      l2_prefetch((const uint8_t*)wo + blockIdx.x * 6400, 6400);
    }
    __syncwarp();
  }
  k3_ffn1_tile<0>(c, m, b1);
  k3_ffn1_tile<1>(c, m, b1);
  float acc[80];
#pragma unroll 1
  for (int g = 0; g < 3; g++) {
#pragma unroll
    for (int i = 0; i < 8; i++) {
      if (i >= 3) k3_mma<160, true>(acc, c, i & 3, ((i >> 2) + 1) & 1, (g | i) == 0);
      else k3_mma<160, false>(acc, c, i & 3, ((i >> 2) + 1) & 1, (g | i) == 0);
      if (c.warp == 1 && ((g == 0 && (i == 1 || i == 4)) || (g == 2 && i == 6))) {
        if (elect_one()) {
          if (i == 1) { bulk_wait_all(); fence_gpu(); flag_add(g_flag + c.rb, 4); }
          else if (i == 4) flag_wait(g_flag + c.rb, 4);
          else { flag_wait(g_flag + 32 + c.rb, 16); fence_async_all(); }
        }
        __syncwarp();
      }
      const bool more = i < 6 || g < 2;
      const int kb = c.j * 6 + 8 * g + i + 2;
      k3_fill(c, (i + 2) & 3, ((i + 2) >> 2) & 1, more ? &m.h : &m.o, more ? &m.w2 : &m.wo, more ? (kb < 24 ? kb : kb - 24) * 64 : (i - 6) * 64, c.j * 5, 10240);
      wg_wait<1>();
      if ((g | i) != 0) k3_release(c, (i - 1) & 3);
    }
  }
  wg_wait<0>();
  reg_fence(acc);
  k3_release(c, 3);
  __syncthreads();
  {
    const int row = c.rb * 64 + c.warp * 16 + (c.lane >> 2);
    const float w0 = bf_hi(__ldcg(g_G + row)), w1 = bf_hi(__ldcg(g_G + row + 8));
#pragma unroll
    for (int i = 0; i < 20; i++) {
      const uint32_t bb = __ldg((const uint32_t*)b2 + c.j * 80 + i * 4 + (c.lane & 3));
      acc[4 * i] = (acc[4 * i] + bf_lo(bb)) * w0; acc[4 * i + 1] = (acc[4 * i + 1] + bf_hi(bb)) * w0;
      acc[4 * i + 2] = (acc[4 * i + 2] + bf_lo(bb)) * w1; acc[4 * i + 3] = (acc[4 * i + 3] + bf_hi(bb)) * w1;
    }
    reg_fence(acc);
  }
  k3_wo_stages<44, 49>(acc, c, m);
  wg_wait<0>();
  k3_release(c, 48 & 3);
  k3_fill_stage<51>(c, m); k3_fill_stage<52>(c, m);
  if (c.warp == 1) {
    if (elect_one()) {
      pdl_wait();
#pragma unroll
      for (int i = 49; i < 53; i++) tma2d(c.s0 + (i & 3) * K3_SB, &m.o, (i - 44) * 64, c.rb * 64, c.full0 + (i & 3) * 8);
    }
    __syncwarp();
  }
  k3_wo_stages<49, 54>(acc, c, m);
  wg_wait<0>();
  reg_fence(acc);
  __syncthreads();
  const uint32_t stg = c.s0 + 3 * K3_SB;
  const int mi = c.lane >> 3, srow = c.warp * 16 + (mi & 1) * 8 + (c.lane & 7);
#pragma unroll
  for (int i = 0; i < 10; i++) {
    const int chunk = ((2 * i) & 3) + (mi >> 1);
    stsm4(stg + (i >> 1) * 4096 + srow * 64 + ((chunk ^ ((srow >> 1) & 3)) << 4), pack(acc[8 * i], acc[8 * i + 1]), pack(acc[8 * i + 2], acc[8 * i + 3]),
          pack(acc[8 * i + 4], acc[8 * i + 5]), pack(acc[8 * i + 6], acc[8 * i + 7]));
  }
  fence_async_smem();
  __syncthreads();
  if (c.warp == 0 && elect_one()) {
    tma3d_store(&m.out, stg, 0, c.rb * 64, c.j * 5);
    bulk_commit();
    bulk_wait_read();
  }
}

typedef CUresult (*EncodeFn)(CUtensorMap*, CUtensorMapDataType, cuuint32_t, void*, const cuuint64_t*, const cuuint64_t*, const cuuint32_t*,
                             const cuuint32_t*, CUtensorMapInterleave, CUtensorMapSwizzle, CUtensorMapL2promotion, CUtensorMapFloatOOBfill);

static void map2d(EncodeFn enc, CUtensorMap* m, const void* p, uint64_t cols, uint64_t rows, uint32_t br) {
  cuuint64_t gd[2] = {cols, rows}, gs[1] = {cols * 2};
  cuuint32_t bd[2] = {64, br}, es[2] = {1, 1};
  enc(m, CU_TENSOR_MAP_DATA_TYPE_BFLOAT16, 2, (void*)p, gd, gs, bd, es, CU_TENSOR_MAP_INTERLEAVE_NONE, CU_TENSOR_MAP_SWIZZLE_128B,
      CU_TENSOR_MAP_L2_PROMOTION_L2_256B, CU_TENSOR_MAP_FLOAT_OOB_FILL_NONE);
}
static void map3d(EncodeFn enc, CUtensorMap* m, const void* p, uint64_t cols, uint64_t rows, uint32_t w, uint32_t br, uint32_t nblk) {
  cuuint64_t gd[3] = {w, rows, cols / w}, gs[2] = {cols * 2, w * 2};
  cuuint32_t bd[3] = {w, br, nblk}, es[3] = {1, 1, 1};
  enc(m, CU_TENSOR_MAP_DATA_TYPE_BFLOAT16, 3, (void*)p, gd, gs, bd, es, CU_TENSOR_MAP_INTERLEAVE_NONE,
      w == 64 ? CU_TENSOR_MAP_SWIZZLE_128B : CU_TENSOR_MAP_SWIZZLE_64B, CU_TENSOR_MAP_L2_PROMOTION_L2_256B, CU_TENSOR_MAP_FLOAT_OOB_FILL_NONE);
}

extern "C" void kernel_launch(void* const* d_in, const int* in_sizes, int n_in, void* d_out, int out_size) {
  const __nv_bfloat16* x = (const __nv_bfloat16*)d_in[0];
  const __nv_bfloat16* wqkv = (const __nv_bfloat16*)d_in[1];
  const __nv_bfloat16* wo = (const __nv_bfloat16*)d_in[2];
  const __nv_bfloat16* w1 = (const __nv_bfloat16*)d_in[4];
  const __nv_bfloat16* b1 = (const __nv_bfloat16*)d_in[5];
  const __nv_bfloat16* w2 = (const __nv_bfloat16*)d_in[6];
  const __nv_bfloat16* b2 = (const __nv_bfloat16*)d_in[7];
  const __nv_bfloat16* gate_w = (const __nv_bfloat16*)d_in[8];

  EncodeFn enc = nullptr;
  cudaDriverEntryPointQueryResult qr;
  cudaGetDriverEntryPoint("cuTensorMapEncodeTiled", (void**)&enc, cudaEnableDefault, &qr);
  void *pH, *pO;
  cudaGetSymbolAddress(&pH, g_H);
  cudaGetSymbolAddress(&pO, g_O);
  CUtensorMap tm_x, tm_wqkv;
  K3Maps m;
  map2d(enc, &tm_x, x, 640, 2048, 128);
  map2d(enc, &tm_wqkv, wqkv, 1920, 640, 64);
  map2d(enc, &m.x, x, 640, 2048, 64);
  map2d(enc, &m.h, pH, 1536, 2048, 64);
  map2d(enc, &m.o, pO, 640, 2048, 64);
  map3d(enc, &m.w1, w1, 1536, 640, 64, 32, 3);
  map3d(enc, &m.w2, w2, 640, 1536, 32, 32, 5);
  map3d(enc, &m.wo, wo, 640, 640, 32, 32, 5);
  map3d(enc, &m.out, d_out, 640, 2048, 32, 64, 5);
  cudaFuncSetAttribute(k_qkv, cudaFuncAttributeMaxDynamicSharedMemorySize, K1_SMEM);
  cudaFuncSetAttribute(k_attn, cudaFuncAttributeMaxDynamicSharedMemorySize, K2_SMEM);
  cudaFuncSetAttribute(k_ffn, cudaFuncAttributeMaxDynamicSharedMemorySize, K3_SMEM);
  cudaFuncSetAttribute(k_qkv, cudaFuncAttributePreferredSharedMemoryCarveout, 100);
  cudaFuncSetAttribute(k_attn, cudaFuncAttributePreferredSharedMemoryCarveout, 100);
  cudaFuncSetAttribute(k_ffn, cudaFuncAttributePreferredSharedMemoryCarveout, 100);

  cudaStream_t st = cudaStreamPerThread;
  k_qkv<<<128, 384, K1_SMEM, st>>>(tm_x, tm_wqkv, x, w1, gate_w);

  cudaLaunchAttribute pdl[1];
  pdl[0].id = cudaLaunchAttributeProgrammaticStreamSerialization;
  pdl[0].val.programmaticStreamSerializationAllowed = 1;
  cudaLaunchConfig_t cfg = {};
  cfg.stream = st; cfg.attrs = pdl; cfg.numAttrs = 1;
  cfg.gridDim = dim3(128); cfg.blockDim = dim3(512); cfg.dynamicSmemBytes = K2_SMEM;
  cudaLaunchKernelEx(&cfg, k_attn);
  cfg.blockDim = dim3(128); cfg.dynamicSmemBytes = K3_SMEM;
  cudaLaunchKernelEx(&cfg, k_ffn, m, b1, b2, w2, wo);
}
```
